```python
import torch

def _softmax(x, axis=-1):
    return torch.softmax(x, dim=axis)
def _gelu(x):
    return torch.nn.functional.gelu(x, approximate="tanh")
def _silu(x):
    return torch.nn.functional.silu(x)
def _sigmoid(x):
    return torch.sigmoid(x)
def _layernorm(x, axis=-1, eps=1e-5):
    m = x.mean(dim=axis, keepdim=True)
    v = x.var(dim=axis, keepdim=True, unbiased=False)
    return (x - m) / torch.sqrt(v + eps)
def _scatter_add(tgt, idx, src, axis=0):
    return tgt.clone().index_add_(axis, idx, src)
def _segment_sum(src, seg, n):
    out = torch.zeros((n,) + src.shape[1:], dtype=src.dtype)
    return out.index_add_(0, seg, src)
def _pad(x, pw):
    flat = tuple(v for pair in reversed(pw) for v in pair)
    return torch.nn.functional.pad(x, flat)

kernel_name = 'standalone__deepnorm__sampling'

def setup_inputs():

    _w = (lambda a: (lambda t: t.to(torch.bfloat16) if t.is_floating_point() else t)(torch.as_tensor(a)))
    B, S, D = 1024, 4, 1024
    return {
        "x": _w((lambda *s: torch.randn(*s, dtype=torch.bfloat16) * 0.05)(B, S, D)),
        "f": _w((lambda *s: torch.randn(*s, dtype=torch.bfloat16) * 0.05)(B, S, D)),
        "g": _w((lambda *s: torch.randn(*s, dtype=torch.bfloat16) * 0.05)(D) + 1.0),
        "b": _w((lambda *s: torch.randn(*s, dtype=torch.bfloat16) * 0.4)(D)),
        "alpha": _w(float(2.0)),
    }

def reference(x, f, g, b, alpha):
    return _layernorm(alpha * x + f, axis=-1) * g + b
```

```cpp
#include <cuda_runtime.h>
#include <cuda_bf16.h>
#include <stdint.h>

static constexpr int D = 1024;
static constexpr int WARPS = 8;

__device__ __forceinline__ uint4 ldg_stream(const uint4* p) {
    uint4 v;
    asm volatile("ld.global.nc.L1::no_allocate.v4.u32 {%0,%1,%2,%3}, [%4];"
                 : "=r"(v.x), "=r"(v.y), "=r"(v.z), "=r"(v.w) : "l"(p));
    return v;
}
__device__ __forceinline__ float bf_lo(uint32_t u) { return __uint_as_float(u << 16); }
__device__ __forceinline__ float bf_hi(uint32_t u) { return __uint_as_float(u & 0xffff0000u); }
__device__ __forceinline__ uint32_t pack2(float lo, float hi) {
    uint32_t r;
    asm("cvt.rn.bf16x2.f32 %0, %1, %2;" : "=r"(r) : "f"(hi), "f"(lo));
    return r;
}

__global__ void __launch_bounds__(WARPS * 32)
deepnorm_kernel(const uint4* __restrict__ x, const uint4* __restrict__ f,
                const uint4* __restrict__ g, const uint4* __restrict__ b,
                const __nv_bfloat16* __restrict__ alpha_p, uint4* __restrict__ out, int rows) {
    const int lane = threadIdx.x & 31;
    const int row = blockIdx.x * WARPS + (threadIdx.x >> 5);
    if (row >= rows) return;
    const size_t base = (size_t)row * (D / 8) + lane;
    uint4 xv[4], fv[4];
#pragma unroll
    for (int i = 0; i < 4; i++) xv[i] = ldg_stream(x + base + i * 32);
#pragma unroll
    for (int i = 0; i < 4; i++) fv[i] = ldg_stream(f + base + i * 32);
    const float alpha = __bfloat162float(*alpha_p);

    float v[32];
    float s = 0.f;
#pragma unroll
    for (int i = 0; i < 4; i++) {
        const uint32_t* xu = reinterpret_cast<const uint32_t*>(&xv[i]);
        const uint32_t* fu = reinterpret_cast<const uint32_t*>(&fv[i]);
#pragma unroll
        for (int j = 0; j < 4; j++) {
            v[i * 8 + 2 * j]     = fmaf(alpha, bf_lo(xu[j]), bf_lo(fu[j]));
            v[i * 8 + 2 * j + 1] = fmaf(alpha, bf_hi(xu[j]), bf_hi(fu[j]));
            s += v[i * 8 + 2 * j] + v[i * 8 + 2 * j + 1];
        }
    }
#pragma unroll
    for (int o = 16; o > 0; o >>= 1) s += __shfl_xor_sync(0xffffffffu, s, o);
    const float mean = s * (1.0f / D);
    float q = 0.f;
#pragma unroll
    for (int i = 0; i < 32; i++) { v[i] -= mean; q = fmaf(v[i], v[i], q); }
#pragma unroll
    for (int o = 16; o > 0; o >>= 1) q += __shfl_xor_sync(0xffffffffu, q, o);
    const float rstd = rsqrtf(q * (1.0f / D) + 1e-5f);
#pragma unroll
    for (int i = 0; i < 4; i++) {
        const uint4 gv = __ldg(g + lane + i * 32);
        const uint4 bv = __ldg(b + lane + i * 32);
        const uint32_t* gu = reinterpret_cast<const uint32_t*>(&gv);
        const uint32_t* bu = reinterpret_cast<const uint32_t*>(&bv);
        uint4 o;
        uint32_t* ou = reinterpret_cast<uint32_t*>(&o);
#pragma unroll
        for (int j = 0; j < 4; j++) {
            float lo = fmaf(v[i * 8 + 2 * j] * rstd, bf_lo(gu[j]), bf_lo(bu[j]));
            float hi = fmaf(v[i * 8 + 2 * j + 1] * rstd, bf_hi(gu[j]), bf_hi(bu[j]));
            ou[j] = pack2(lo, hi);
        }
        out[base + i * 32] = o;
    }
}

extern "C" void kernel_launch(void* const* d_in, const int* in_sizes, int n_in,
                              void* d_out, int out_size) {
    const uint4* x = (const uint4*)d_in[0];
    const uint4* f = (const uint4*)d_in[1];
    const uint4* g = (const uint4*)d_in[2];
    const uint4* b = (const uint4*)d_in[3];
    const __nv_bfloat16* alpha = (const __nv_bfloat16*)d_in[4];
    const int rows = in_sizes[0] / D;
    deepnorm_kernel<<<(rows + WARPS - 1) / WARPS, WARPS * 32>>>(x, f, g, b, alpha, (uint4*)d_out, rows);
}
```

```cpp
#include <cuda_runtime.h>
#include <cuda_bf16.h>
#include <stdint.h>

static constexpr int D = 1024;
static constexpr int WARPS = 8;
static constexpr int STAG = 400;
static constexpr int NSTAG = 4;

__device__ __forceinline__ uint4 ldg_stream(const uint4* p) {
    uint4 v;
    asm volatile("ld.global.nc.L1::no_allocate.v4.u32 {%0,%1,%2,%3}, [%4];"
                 : "=r"(v.x), "=r"(v.y), "=r"(v.z), "=r"(v.w) : "l"(p) : "memory");
    return v;
}
__device__ __forceinline__ uint4 ldg_cached(const uint4* p) {
    uint4 v;
    asm volatile("ld.global.nc.v4.u32 {%0,%1,%2,%3}, [%4];"
                 : "=r"(v.x), "=r"(v.y), "=r"(v.z), "=r"(v.w) : "l"(p) : "memory");
    return v;
}
__device__ __forceinline__ unsigned clk() {
    unsigned t; asm volatile("mov.u32 %0, %clock;" : "=r"(t) :: "memory"); return t;
}
__device__ __forceinline__ float bf_lo(uint32_t u) { return __uint_as_float(u << 16); }
__device__ __forceinline__ float bf_hi(uint32_t u) { return __uint_as_float(u & 0xffff0000u); }
__device__ __forceinline__ uint32_t pack2(float lo, float hi) {
    uint32_t r;
    asm("cvt.rn.bf16x2.f32 %0, %1, %2;" : "=r"(r) : "f"(hi), "f"(lo));
    return r;
}
__device__ __forceinline__ uint32_t hfma2_v(uint32_t a, uint32_t b, uint32_t c) {
    uint32_t d; asm volatile("fma.rn.bf16x2 %0, %1, %2, %3;" : "=r"(d) : "r"(a), "r"(b), "r"(c)); return d;
}
__device__ __forceinline__ uint32_t hfma2(uint32_t a, uint32_t b, uint32_t c) {
    uint32_t d; asm("fma.rn.bf16x2 %0, %1, %2, %3;" : "=r"(d) : "r"(a), "r"(b), "r"(c)); return d;
}
__device__ __forceinline__ float rsqrt_ftz(float x) {
    float r; asm("rsqrt.approx.ftz.f32 %0, %1;" : "=f"(r) : "f"(x)); return r;
}

__device__ __forceinline__ void residual(uint32_t (&h)[16], uint32_t a2, const uint4 (&xa)[4], const uint4 (&fa)[4]) {
#pragma unroll
    for (int i = 0; i < 4; i++) {
        h[i * 4 + 0] = hfma2_v(a2, xa[i].x, fa[i].x); h[i * 4 + 1] = hfma2_v(a2, xa[i].y, fa[i].y);
        h[i * 4 + 2] = hfma2_v(a2, xa[i].z, fa[i].z); h[i * 4 + 3] = hfma2_v(a2, xa[i].w, fa[i].w);
    }
}
__device__ __forceinline__ void load_row(uint4 (&xa)[4], uint4 (&fa)[4], const uint4* px, const uint4* pf) {
#pragma unroll
    for (int i = 0; i < 4; i++) { xa[i] = ldg_stream(px + i * 32); fa[i] = ldg_stream(pf + i * 32); }
}
__device__ __forceinline__ void store_row(uint4* po, const uint4 (&o)[4]) {
#pragma unroll
    for (int i = 0; i < 4; i++) po[i * 32] = o[i];
}
__device__ __forceinline__ void norm_row(uint4 (&o)[4], const uint32_t (&h)[16], const uint4 (&gp)[4], const uint4 (&bp)[4]) {
    float v[32];
#pragma unroll
    for (int i = 0; i < 16; i++) { v[2 * i] = bf_lo(h[i]); v[2 * i + 1] = bf_hi(h[i]); }
    const float K = __shfl_sync(0xffffffffu, v[0], 0);
    float s0 = 0.f, s1 = 0.f, s2 = 0.f, s3 = 0.f, q0 = 0.f, q1 = 0.f, q2 = 0.f, q3 = 0.f;
#pragma unroll
    for (int i = 0; i < 8; i++) {
        v[i] -= K; v[8 + i] -= K; v[16 + i] -= K; v[24 + i] -= K;
        s0 += v[i]; s1 += v[8 + i]; s2 += v[16 + i]; s3 += v[24 + i];
        q0 = fmaf(v[i], v[i], q0); q1 = fmaf(v[8 + i], v[8 + i], q1);
        q2 = fmaf(v[16 + i], v[16 + i], q2); q3 = fmaf(v[24 + i], v[24 + i], q3);
    }
    float s = (s0 + s1) + (s2 + s3), q = (q0 + q1) + (q2 + q3);
#pragma unroll
    for (int ofs = 16; ofs > 0; ofs >>= 1) {
        s += __shfl_xor_sync(0xffffffffu, s, ofs);
        q += __shfl_xor_sync(0xffffffffu, q, ofs);
    }
    const float mean = s * (1.0f / D);
    const float ve = fmaxf(fmaf(-mean, mean, fmaf(q, 1.0f / D, 1e-5f)), 1e-5f);
    const float rstd = rsqrt_ftz(ve);
    const float nmr = -mean * rstd;
#pragma unroll
    for (int i = 0; i < 4; i++) {
        float t[8];
#pragma unroll
        for (int j = 0; j < 8; j++) t[j] = fmaf(v[i * 8 + j], rstd, nmr);
        o[i].x = hfma2(pack2(t[0], t[1]), gp[i].x, bp[i].x);
        o[i].y = hfma2(pack2(t[2], t[3]), gp[i].y, bp[i].y);
        o[i].z = hfma2(pack2(t[4], t[5]), gp[i].z, bp[i].z);
        o[i].w = hfma2(pack2(t[6], t[7]), gp[i].w, bp[i].w);
    }
}

__global__ void __launch_bounds__(WARPS * 32, 1)
deepnorm_fixed(const uint4* __restrict__ x, const uint4* __restrict__ f,
               const uint4* __restrict__ g, const uint4* __restrict__ b,
               const unsigned short* __restrict__ alpha_p, uint4* __restrict__ out) {
    constexpr int NR = 4;
    constexpr int ROW = D / 8;
    constexpr int STEP = 256 * ROW;
    const int lane = threadIdx.x & 31, warp = threadIdx.x >> 5;
    const uint32_t off = (uint32_t)(blockIdx.x + 128 * (warp & 1) + 1024 * (warp >> 1)) * ROW + lane;
    const uint4* px = x + off;
    const uint4* pf = f + off;
    uint4* po = out + off;
    uint4 gp[4], bp[4], xa[4], fa[4], o[4];
    uint32_t h[16];
    const unsigned grp = warp / (WARPS / NSTAG);
    const unsigned t0 = clk();
#pragma unroll
    for (int i = 0; i < 4; i++) { gp[i] = ldg_cached(g + lane + i * 32); bp[i] = ldg_cached(b + lane + i * 32); }
    const uint32_t a16 = *alpha_p;
    if (grp > 0) { while (clk() - t0 < STAG * grp) {} }
    load_row(xa, fa, px, pf);
    const uint32_t a2 = a16 | (a16 << 16);
#pragma unroll 1
    for (int it = 0; it < NR - 1; it++) {
        residual(h, a2, xa, fa);
        px += STEP; pf += STEP;
        load_row(xa, fa, px, pf);
        norm_row(o, h, gp, bp);
        if (it < NR - 2) store_row(po, o);
        po += STEP;
    }
    residual(h, a2, xa, fa);
    store_row(po - STEP, o);
    norm_row(o, h, gp, bp);
    store_row(po, o);
}

__global__ void __launch_bounds__(WARPS * 32, 1)
deepnorm_generic(const uint4* __restrict__ x, const uint4* __restrict__ f,
                 const uint4* __restrict__ g, const uint4* __restrict__ b,
                 const unsigned short* __restrict__ alpha_p, uint4* __restrict__ out, int rows) {
    const int lane = threadIdx.x & 31, warp = threadIdx.x >> 5;
    const int tw = gridDim.x * WARPS;
    uint4 gp[4], bp[4], xa[4], fa[4], o[4];
    uint32_t h[16];
#pragma unroll
    for (int i = 0; i < 4; i++) { gp[i] = ldg_cached(g + lane + i * 32); bp[i] = ldg_cached(b + lane + i * 32); }
    const uint32_t a16 = *alpha_p;
    const uint32_t a2 = a16 | (a16 << 16);
#pragma unroll 1
    for (int row = blockIdx.x + warp * gridDim.x; row < rows; row += tw) {
        const size_t base = (size_t)row * (D / 8) + lane;
        load_row(xa, fa, x + base, f + base);
        residual(h, a2, xa, fa);
        norm_row(o, h, gp, bp);
        store_row(out + base, o);
    }
}

extern "C" void kernel_launch(void* const* d_in, const int* in_sizes, int n_in,
                              void* d_out, int out_size) {
    const uint4* x = (const uint4*)d_in[0];
    const uint4* f = (const uint4*)d_in[1];
    const uint4* g = (const uint4*)d_in[2];
    const uint4* b = (const uint4*)d_in[3];
    const unsigned short* alpha = (const unsigned short*)d_in[4];
    const int rows = in_sizes[0] / D;
    if (rows == 4096)
        deepnorm_fixed<<<128, WARPS * 32>>>(x, f, g, b, alpha, (uint4*)d_out);
    else
        deepnorm_generic<<<128, WARPS * 32>>>(x, f, g, b, alpha, (uint4*)d_out, rows);
}
```
